```python
import torch

def _softmax(x, axis=-1):
    return torch.softmax(x, dim=axis)
def _gelu(x):
    return torch.nn.functional.gelu(x, approximate="tanh")
def _silu(x):
    return torch.nn.functional.silu(x)
def _sigmoid(x):
    return torch.sigmoid(x)
def _layernorm(x, axis=-1, eps=1e-5):
    m = x.mean(dim=axis, keepdim=True)
    v = x.var(dim=axis, keepdim=True, unbiased=False)
    return (x - m) / torch.sqrt(v + eps)
def _scatter_add(tgt, idx, src, axis=0):
    return tgt.clone().index_add_(axis, idx, src)
def _segment_sum(src, seg, n):
    out = torch.zeros((n,) + src.shape[1:], dtype=src.dtype)
    return out.index_add_(0, seg, src)
def _pad(x, pw):
    flat = tuple(v for pair in reversed(pw) for v in pair)
    return torch.nn.functional.pad(x, flat)

kernel_name = 'standalone__mha_block_cached__near_ridge'

def setup_inputs():

    _w = (lambda a: (lambda t: t.to(torch.bfloat16) if t.is_floating_point() else t)(torch.as_tensor(a)))
    B, Sq, D = 16, 128, 1024
    H, Sk, Dh = 32, 512, 128
    return {
        "x": _w((lambda *s: torch.randn(*s, dtype=torch.bfloat16) * 0.8)(B, Sq, D)),
        "k_cache": _w((lambda *s: torch.randn(*s, dtype=torch.bfloat16) * 0.8)(B, H, Sk, Dh)),
        "v_cache": _w((lambda *s: torch.randn(*s, dtype=torch.bfloat16) * 0.05)(B, H, Sk, Dh)),
        "wq": _w((lambda *s: torch.randn(*s, dtype=torch.bfloat16) * 0.8)(D, H * Dh) * (D ** -0.5)),
        "wo": _w((lambda *s: torch.randn(*s, dtype=torch.bfloat16) * 0.05)(H * Dh, D) * ((H * Dh) ** -0.5)),
    }

def reference(x, k_cache, v_cache, wq, wo):
    B, Sq, D = x.shape
    H, Dh = 32, 128
    q = (lambda x, *d: x.permute(*d))((x @ wq).reshape(B, Sq, H, Dh), 0, 2, 1, 3)
    scores = torch.einsum("bhqd,bhkd->bhqk", q, k_cache) * (Dh ** -0.5)
    p = _softmax(scores, axis=-1)
    o = torch.einsum("bhqk,bhkd->bhqd", p, v_cache)
    return (lambda x, *d: x.permute(*d))(o, 0, 2, 1, 3).reshape(B, Sq, H * Dh) @ wo
```

```cpp
#include <cuda_runtime.h>
#include <cuda_bf16.h>
#include <cuda.h>
#include <stdint.h>

namespace {

constexpr int kB = 16, kSQ = 128, kD = 1024, kH = 32, kSK = 512, kDH = 128;
constexpr int kM = kB * kSQ;
constexpr int kHD = kH * kDH;

constexpr int SLOT_BYTES = 32768;
constexpr int NSLOT = 6;
constexpr int RING_BYTES = SLOT_BYTES * NSLOT;
constexpr int QPARK_BYTES = 32768;
constexpr int SMEM_A = RING_BYTES + QPARK_BYTES + 1024;
constexpr int SMEM_B = RING_BYTES + 1024;

__device__ __nv_bfloat16 g_O[(size_t)kM * kHD];

#define TS(idx) do {} while (0)

__device__ __forceinline__ uint32_t smem_u32(const void* p) { return (uint32_t)__cvta_generic_to_shared(p); }

__device__ __forceinline__ void mbar_init(uint32_t bar, uint32_t count) {
  asm volatile("mbarrier.init.shared::cta.b64 [%0], %1;" ::"r"(bar), "r"(count) : "memory");
}
__device__ __forceinline__ void mbar_expect_tx(uint32_t bar, uint32_t bytes) {
  asm volatile("mbarrier.arrive.expect_tx.shared::cta.b64 _, [%0], %1;" ::"r"(bar), "r"(bytes) : "memory");
}
__device__ __forceinline__ void mbar_arrive(uint32_t bar) {
  asm volatile("mbarrier.arrive.shared::cta.b64 _, [%0];" ::"r"(bar) : "memory");
}
__device__ __forceinline__ bool mbar_try_wait(uint32_t bar, uint32_t parity) {
  uint32_t ok;
  asm volatile(
      "{\n.reg .pred p;\nmbarrier.try_wait.parity.shared::cta.b64 p, [%1], %2;\nselp.u32 %0, 1, 0, p;\n}"
      : "=r"(ok)
      : "r"(bar), "r"(parity)
      : "memory");
  return ok != 0;
}
__device__ __forceinline__ void mbar_wait(uint32_t bar, uint32_t parity) {
  uint32_t n = 0;
  while (!mbar_try_wait(bar, parity)) {
    if (++n > (1u << 21)) break;
  }
}
__device__ __forceinline__ void tma_load_2d(uint32_t dst, const CUtensorMap* map, int c0, int c1, uint32_t bar) {
  asm volatile(
      "cp.async.bulk.tensor.2d.shared::cluster.global.mbarrier::complete_tx::bytes [%0], [%1, {%3, %4}], [%2];"
      ::"r"(dst), "l"(map), "r"(bar), "r"(c0), "r"(c1)
      : "memory");
}
__device__ __forceinline__ void tma_load_2d_hint(uint32_t dst, const CUtensorMap* map, int c0, int c1, uint32_t bar,
                                                 uint64_t policy) {
  asm volatile(
      "cp.async.bulk.tensor.2d.shared::cluster.global.mbarrier::complete_tx::bytes.L2::cache_hint [%0], [%1, {%3, "
      "%4}], [%2], %5;" ::"r"(dst),
      "l"(map), "r"(bar), "r"(c0), "r"(c1), "l"(policy)
      : "memory");
}
__device__ __forceinline__ uint64_t policy_evict_first() {
  uint64_t p;
  asm volatile("createpolicy.fractional.L2::evict_first.b64 %0, 1.0;" : "=l"(p));
  return p;
}
__device__ __forceinline__ void tma_prefetch_2d(const CUtensorMap* map, int c0, int c1) {
  asm volatile("cp.async.bulk.prefetch.tensor.2d.L2.global.tile [%0, {%1, %2}];" ::"l"(map), "r"(c0), "r"(c1)
               : "memory");
}
__device__ __forceinline__ void tma_store_2d(const CUtensorMap* map, int c0, int c1, uint32_t src) {
  asm volatile("cp.async.bulk.tensor.2d.global.shared::cta.bulk_group [%0, {%1, %2}], [%3];" ::"l"(map), "r"(c0),
               "r"(c1), "r"(src)
               : "memory");
}
__device__ __forceinline__ void bulk_commit() { asm volatile("cp.async.bulk.commit_group;" ::: "memory"); }
__device__ __forceinline__ void bulk_wait_read0() { asm volatile("cp.async.bulk.wait_group.read 0;" ::: "memory"); }
__device__ __forceinline__ void bulk_wait0() { asm volatile("cp.async.bulk.wait_group 0;" ::: "memory"); }
__device__ __forceinline__ void fence_proxy_async() { asm volatile("fence.proxy.async.shared::cta;" ::: "memory"); }
__device__ __forceinline__ void wgmma_fence() { asm volatile("wgmma.fence.sync.aligned;" ::: "memory"); }
__device__ __forceinline__ void wgmma_commit() { asm volatile("wgmma.commit_group.sync.aligned;" ::: "memory"); }
template <int N>
__device__ __forceinline__ void wgmma_wait() {
  asm volatile("wgmma.wait_group.sync.aligned %0;" ::"n"(N) : "memory");
}
template <int N>
__device__ __forceinline__ void fence_regs(float (&r)[N]) {
#pragma unroll
  for (int i = 0; i < N; i++) asm volatile("" : "+f"(r[i])::"memory");
}
template <int N>
__device__ __forceinline__ void fence_regs_u(uint32_t (&r)[N]) {
#pragma unroll
  for (int i = 0; i < N; i++) asm volatile("" : "+r"(r[i])::"memory");
}
__device__ __forceinline__ float ex2(float x) {
  float y;
  asm("ex2.approx.ftz.f32 %0, %1;" : "=f"(y) : "f"(x));
  return y;
}
__device__ __forceinline__ uint32_t pack_bf16(float lo, float hi) {
  uint32_t r;
  asm("cvt.rn.bf16x2.f32 %0, %1, %2;" : "=r"(r) : "f"(hi), "f"(lo));
  return r;
}
__device__ __forceinline__ void cluster_sync_all() {
  asm volatile("barrier.cluster.arrive.release.aligned;\nbarrier.cluster.wait.acquire.aligned;" ::: "memory");
}

__device__ __forceinline__ uint64_t desc_kmajor(uint32_t addr) {
  return (uint64_t)((addr & 0x3FFFF) >> 4) | ((uint64_t)1 << 16) | ((uint64_t)(1024 >> 4) << 32) |
         ((uint64_t)1 << 62);
}
__device__ __forceinline__ uint64_t desc_mnmajor(uint32_t addr, uint32_t lbo) {
  return (uint64_t)((addr & 0x3FFFF) >> 4) | ((uint64_t)(lbo >> 4) << 16) | ((uint64_t)(1024 >> 4) << 32) |
         ((uint64_t)1 << 62);
}

__device__ __forceinline__ void wgmma_m64n256k16_ss_tb1(float (&d)[128], uint64_t descA, uint64_t descB, int scale_d) {
  asm volatile("{\n.reg .pred p;\nsetp.ne.b32 p, %130, 0;\n"
    "wgmma.mma_async.sync.aligned.m64n256k16.f32.bf16.bf16 {%0, %1, %2, %3, %4, %5, %6, %7, %8, %9, %10, %11, %12, %13, %14, %15, %16, %17, %18, %19, %20, %21, %22, %23, %24, %25, %26, %27, %28, %29, %30, %31, %32, %33, %34, %35, %36, %37, %38, %39, %40, %41, %42, %43, %44, %45, %46, %47, %48, %49, %50, %51, %52, %53, %54, %55, %56, %57, %58, %59, %60, %61, %62, %63, %64, %65, %66, %67, %68, %69, %70, %71, %72, %73, %74, %75, %76, %77, %78, %79, %80, %81, %82, %83, %84, %85, %86, %87, %88, %89, %90, %91, %92, %93, %94, %95, %96, %97, %98, %99, %100, %101, %102, %103, %104, %105, %106, %107, %108, %109, %110, %111, %112, %113, %114, %115, %116, %117, %118, %119, %120, %121, %122, %123, %124, %125, %126, %127}, %128, %129, p, 1, 1, 0, 1;\n}\n"
    : "+f"(d[0]), "+f"(d[1]), "+f"(d[2]), "+f"(d[3]), "+f"(d[4]), "+f"(d[5]), "+f"(d[6]), "+f"(d[7]), "+f"(d[8]), "+f"(d[9]), "+f"(d[10]), "+f"(d[11]), "+f"(d[12]), "+f"(d[13]), "+f"(d[14]), "+f"(d[15]), "+f"(d[16]), "+f"(d[17]), "+f"(d[18]), "+f"(d[19]), "+f"(d[20]), "+f"(d[21]), "+f"(d[22]), "+f"(d[23]), "+f"(d[24]), "+f"(d[25]), "+f"(d[26]), "+f"(d[27]), "+f"(d[28]), "+f"(d[29]), "+f"(d[30]), "+f"(d[31]), "+f"(d[32]), "+f"(d[33]), "+f"(d[34]), "+f"(d[35]), "+f"(d[36]), "+f"(d[37]), "+f"(d[38]), "+f"(d[39]), "+f"(d[40]), "+f"(d[41]), "+f"(d[42]), "+f"(d[43]), "+f"(d[44]), "+f"(d[45]), "+f"(d[46]), "+f"(d[47]), "+f"(d[48]), "+f"(d[49]), "+f"(d[50]), "+f"(d[51]), "+f"(d[52]), "+f"(d[53]), "+f"(d[54]), "+f"(d[55]), "+f"(d[56]), "+f"(d[57]), "+f"(d[58]), "+f"(d[59]), "+f"(d[60]), "+f"(d[61]), "+f"(d[62]), "+f"(d[63]), "+f"(d[64]), "+f"(d[65]), "+f"(d[66]), "+f"(d[67]), "+f"(d[68]), "+f"(d[69]), "+f"(d[70]), "+f"(d[71]), "+f"(d[72]), "+f"(d[73]), "+f"(d[74]), "+f"(d[75]), "+f"(d[76]), "+f"(d[77]), "+f"(d[78]), "+f"(d[79]), "+f"(d[80]), "+f"(d[81]), "+f"(d[82]), "+f"(d[83]), "+f"(d[84]), "+f"(d[85]), "+f"(d[86]), "+f"(d[87]), "+f"(d[88]), "+f"(d[89]), "+f"(d[90]), "+f"(d[91]), "+f"(d[92]), "+f"(d[93]), "+f"(d[94]), "+f"(d[95]), "+f"(d[96]), "+f"(d[97]), "+f"(d[98]), "+f"(d[99]), "+f"(d[100]), "+f"(d[101]), "+f"(d[102]), "+f"(d[103]), "+f"(d[104]), "+f"(d[105]), "+f"(d[106]), "+f"(d[107]), "+f"(d[108]), "+f"(d[109]), "+f"(d[110]), "+f"(d[111]), "+f"(d[112]), "+f"(d[113]), "+f"(d[114]), "+f"(d[115]), "+f"(d[116]), "+f"(d[117]), "+f"(d[118]), "+f"(d[119]), "+f"(d[120]), "+f"(d[121]), "+f"(d[122]), "+f"(d[123]), "+f"(d[124]), "+f"(d[125]), "+f"(d[126]), "+f"(d[127])
    : "l"(descA), "l"(descB), "r"(scale_d));
}
__device__ __forceinline__ void wgmma_m64n128k16_ss_tb1(float (&d)[64], uint64_t descA, uint64_t descB, int scale_d) {
  asm volatile("{\n.reg .pred p;\nsetp.ne.b32 p, %66, 0;\n"
    "wgmma.mma_async.sync.aligned.m64n128k16.f32.bf16.bf16 {%0, %1, %2, %3, %4, %5, %6, %7, %8, %9, %10, %11, %12, %13, %14, %15, %16, %17, %18, %19, %20, %21, %22, %23, %24, %25, %26, %27, %28, %29, %30, %31, %32, %33, %34, %35, %36, %37, %38, %39, %40, %41, %42, %43, %44, %45, %46, %47, %48, %49, %50, %51, %52, %53, %54, %55, %56, %57, %58, %59, %60, %61, %62, %63}, %64, %65, p, 1, 1, 0, 1;\n}\n"
    : "+f"(d[0]), "+f"(d[1]), "+f"(d[2]), "+f"(d[3]), "+f"(d[4]), "+f"(d[5]), "+f"(d[6]), "+f"(d[7]), "+f"(d[8]), "+f"(d[9]), "+f"(d[10]), "+f"(d[11]), "+f"(d[12]), "+f"(d[13]), "+f"(d[14]), "+f"(d[15]), "+f"(d[16]), "+f"(d[17]), "+f"(d[18]), "+f"(d[19]), "+f"(d[20]), "+f"(d[21]), "+f"(d[22]), "+f"(d[23]), "+f"(d[24]), "+f"(d[25]), "+f"(d[26]), "+f"(d[27]), "+f"(d[28]), "+f"(d[29]), "+f"(d[30]), "+f"(d[31]), "+f"(d[32]), "+f"(d[33]), "+f"(d[34]), "+f"(d[35]), "+f"(d[36]), "+f"(d[37]), "+f"(d[38]), "+f"(d[39]), "+f"(d[40]), "+f"(d[41]), "+f"(d[42]), "+f"(d[43]), "+f"(d[44]), "+f"(d[45]), "+f"(d[46]), "+f"(d[47]), "+f"(d[48]), "+f"(d[49]), "+f"(d[50]), "+f"(d[51]), "+f"(d[52]), "+f"(d[53]), "+f"(d[54]), "+f"(d[55]), "+f"(d[56]), "+f"(d[57]), "+f"(d[58]), "+f"(d[59]), "+f"(d[60]), "+f"(d[61]), "+f"(d[62]), "+f"(d[63])
    : "l"(descA), "l"(descB), "r"(scale_d));
}
__device__ __forceinline__ void wgmma_m64n128k16_rs_tb0(float (&d)[64], uint32_t a0, uint32_t a1, uint32_t a2, uint32_t a3, uint64_t descB, int scale_d) {
  asm volatile("{\n.reg .pred p;\nsetp.ne.b32 p, %69, 0;\n"
    "wgmma.mma_async.sync.aligned.m64n128k16.f32.bf16.bf16 {%0, %1, %2, %3, %4, %5, %6, %7, %8, %9, %10, %11, %12, %13, %14, %15, %16, %17, %18, %19, %20, %21, %22, %23, %24, %25, %26, %27, %28, %29, %30, %31, %32, %33, %34, %35, %36, %37, %38, %39, %40, %41, %42, %43, %44, %45, %46, %47, %48, %49, %50, %51, %52, %53, %54, %55, %56, %57, %58, %59, %60, %61, %62, %63}, {%64, %65, %66, %67}, %68, p, 1, 1, 0;\n}\n"
    : "+f"(d[0]), "+f"(d[1]), "+f"(d[2]), "+f"(d[3]), "+f"(d[4]), "+f"(d[5]), "+f"(d[6]), "+f"(d[7]), "+f"(d[8]), "+f"(d[9]), "+f"(d[10]), "+f"(d[11]), "+f"(d[12]), "+f"(d[13]), "+f"(d[14]), "+f"(d[15]), "+f"(d[16]), "+f"(d[17]), "+f"(d[18]), "+f"(d[19]), "+f"(d[20]), "+f"(d[21]), "+f"(d[22]), "+f"(d[23]), "+f"(d[24]), "+f"(d[25]), "+f"(d[26]), "+f"(d[27]), "+f"(d[28]), "+f"(d[29]), "+f"(d[30]), "+f"(d[31]), "+f"(d[32]), "+f"(d[33]), "+f"(d[34]), "+f"(d[35]), "+f"(d[36]), "+f"(d[37]), "+f"(d[38]), "+f"(d[39]), "+f"(d[40]), "+f"(d[41]), "+f"(d[42]), "+f"(d[43]), "+f"(d[44]), "+f"(d[45]), "+f"(d[46]), "+f"(d[47]), "+f"(d[48]), "+f"(d[49]), "+f"(d[50]), "+f"(d[51]), "+f"(d[52]), "+f"(d[53]), "+f"(d[54]), "+f"(d[55]), "+f"(d[56]), "+f"(d[57]), "+f"(d[58]), "+f"(d[59]), "+f"(d[60]), "+f"(d[61]), "+f"(d[62]), "+f"(d[63])
    : "r"(a0), "r"(a1), "r"(a2), "r"(a3), "l"(descB), "r"(scale_d));
}
__device__ __forceinline__ void wgmma_m64n128k16_rs_tb1(float (&d)[64], uint32_t a0, uint32_t a1, uint32_t a2, uint32_t a3, uint64_t descB, int scale_d) {
  asm volatile("{\n.reg .pred p;\nsetp.ne.b32 p, %69, 0;\n"
    "wgmma.mma_async.sync.aligned.m64n128k16.f32.bf16.bf16 {%0, %1, %2, %3, %4, %5, %6, %7, %8, %9, %10, %11, %12, %13, %14, %15, %16, %17, %18, %19, %20, %21, %22, %23, %24, %25, %26, %27, %28, %29, %30, %31, %32, %33, %34, %35, %36, %37, %38, %39, %40, %41, %42, %43, %44, %45, %46, %47, %48, %49, %50, %51, %52, %53, %54, %55, %56, %57, %58, %59, %60, %61, %62, %63}, {%64, %65, %66, %67}, %68, p, 1, 1, 1;\n}\n"
    : "+f"(d[0]), "+f"(d[1]), "+f"(d[2]), "+f"(d[3]), "+f"(d[4]), "+f"(d[5]), "+f"(d[6]), "+f"(d[7]), "+f"(d[8]), "+f"(d[9]), "+f"(d[10]), "+f"(d[11]), "+f"(d[12]), "+f"(d[13]), "+f"(d[14]), "+f"(d[15]), "+f"(d[16]), "+f"(d[17]), "+f"(d[18]), "+f"(d[19]), "+f"(d[20]), "+f"(d[21]), "+f"(d[22]), "+f"(d[23]), "+f"(d[24]), "+f"(d[25]), "+f"(d[26]), "+f"(d[27]), "+f"(d[28]), "+f"(d[29]), "+f"(d[30]), "+f"(d[31]), "+f"(d[32]), "+f"(d[33]), "+f"(d[34]), "+f"(d[35]), "+f"(d[36]), "+f"(d[37]), "+f"(d[38]), "+f"(d[39]), "+f"(d[40]), "+f"(d[41]), "+f"(d[42]), "+f"(d[43]), "+f"(d[44]), "+f"(d[45]), "+f"(d[46]), "+f"(d[47]), "+f"(d[48]), "+f"(d[49]), "+f"(d[50]), "+f"(d[51]), "+f"(d[52]), "+f"(d[53]), "+f"(d[54]), "+f"(d[55]), "+f"(d[56]), "+f"(d[57]), "+f"(d[58]), "+f"(d[59]), "+f"(d[60]), "+f"(d[61]), "+f"(d[62]), "+f"(d[63])
    : "r"(a0), "r"(a1), "r"(a2), "r"(a3), "l"(descB), "r"(scale_d));
}

struct Ring {
  uint32_t slot = 0, phase = 0;
  __device__ __forceinline__ void advance() {
    if (++slot == NSLOT) {
      slot = 0;
      phase ^= 1;
    }
  }
};

__device__ __forceinline__ void gemm_consume_128x256(float (&acc)[128], int nsteps, Ring& ring, uint32_t sbase,
                                                     uint32_t full0, uint32_t empty0, int cw, int lane) {
  int prev_w = -1, prev_x = -1;
  int first = 1;
  for (int ks = 0; ks < nsteps; ks++) {
    uint32_t xs = ring.slot;
    mbar_wait(full0 + xs * 8, ring.phase);
    ring.advance();
#pragma unroll
    for (int half = 0; half < 2; half++) {
      uint32_t ws = ring.slot;
      mbar_wait(full0 + ws * 8, ring.phase);
      ring.advance();
      uint32_t xaddr = sbase + xs * SLOT_BYTES + half * 16384 + cw * 8192;
      uint32_t waddr = sbase + ws * SLOT_BYTES;
      wgmma_fence();
#pragma unroll
      for (int kk = 0; kk < 4; kk++) {
        wgmma_m64n256k16_ss_tb1(acc, desc_kmajor(xaddr + kk * 32), desc_mnmajor(waddr + kk * 2048, 8192),
                                first ? 0 : 1);
        first = 0;
      }
      wgmma_commit();
      wgmma_wait<1>();
      if (lane == 0) {
        if (prev_w >= 0) mbar_arrive(empty0 + prev_w * 8);
        if (prev_x >= 0) mbar_arrive(empty0 + prev_x * 8);
      }
      prev_w = (int)ws;
      prev_x = (half == 1) ? (int)xs : -1;
    }
  }
  wgmma_wait<0>();
  fence_regs(acc);
  if (lane == 0) {
    if (prev_w >= 0) mbar_arrive(empty0 + prev_w * 8);
    if (prev_x >= 0) mbar_arrive(empty0 + prev_x * 8);
  }
}

__device__ __forceinline__ void gemm_consume_128x128(float (&acc)[64], int nsteps, Ring& ring, uint32_t sbase,
                                                     uint32_t full0, uint32_t empty0, int cw, int lane) {
  int prev_w = -1, prev_x = -1;
  int first = 1;
  for (int ks = 0; ks < nsteps; ks++) {
    uint32_t xs = ring.slot;
    mbar_wait(full0 + xs * 8, ring.phase);
    ring.advance();
    uint32_t ws = ring.slot;
    mbar_wait(full0 + ws * 8, ring.phase);
    ring.advance();
    uint32_t xaddr = sbase + xs * SLOT_BYTES + cw * 8192;
    uint32_t waddr = sbase + ws * SLOT_BYTES;
    wgmma_fence();
#pragma unroll
    for (int kk = 0; kk < 8; kk++) {
      wgmma_m64n128k16_ss_tb1(acc, desc_kmajor(xaddr + (kk >> 2) * 16384 + (kk & 3) * 32),
                              desc_mnmajor(waddr + kk * 2048, 16384), first ? 0 : 1);
      first = 0;
    }
    wgmma_commit();
    wgmma_wait<1>();
    if (lane == 0) {
      if (prev_w >= 0) mbar_arrive(empty0 + prev_w * 8);
      if (prev_x >= 0) mbar_arrive(empty0 + prev_x * 8);
    }
    prev_w = (int)ws;
    prev_x = (int)xs;
  }
  wgmma_wait<0>();
  fence_regs(acc);
  if (lane == 0) {
    if (prev_w >= 0) mbar_arrive(empty0 + prev_w * 8);
    if (prev_x >= 0) mbar_arrive(empty0 + prev_x * 8);
  }
}

__global__ void __launch_bounds__(384, 1)
attn_kernel(const __grid_constant__ CUtensorMap mx, const __grid_constant__ CUtensorMap mwq,
            const __grid_constant__ CUtensorMap mk, const __grid_constant__ CUtensorMap mv,
            const __grid_constant__ CUtensorMap mos) {
  extern __shared__ uint8_t smem_raw[];
  __shared__ __align__(8) uint64_t full_bar[NSLOT];
  __shared__ __align__(8) uint64_t empty_bar[NSLOT];
  const uint32_t sbase = (smem_u32(smem_raw) + 1023u) & ~1023u;
  const uint32_t full0 = smem_u32(&full_bar[0]);
  const uint32_t empty0 = smem_u32(&empty_bar[0]);
  const int tid = threadIdx.x;
  const int wg = __shfl_sync(0xffffffffu, tid >> 7, 0);
  const int lane = tid & 31;
  const int b = blockIdx.x >> 3;
  const int g = blockIdx.x & 7;
  const int odd = g & 1;
  const int npass = odd ? 3 : 2;
  asm volatile("griddepcontrol.launch_dependents;");

  if (tid == 0) {
    for (int s = 0; s < NSLOT; s++) {
      mbar_init(full0 + s * 8, 1);
      mbar_init(empty0 + s * 8, 8);
    }
    asm volatile("fence.mbarrier_init.release.cluster;" ::: "memory");
    asm volatile("fence.proxy.async.shared::cta;" ::: "memory");
  }
  __syncthreads();

  if (wg == 0) {
    asm volatile("setmaxnreg.dec.sync.aligned.u32 24;");
    if (tid == 0) {
      Ring ring;
      const uint64_t pol_kv = policy_evict_first();
      for (int ps = 0; ps < npass; ps++) {
        const int hfirst = odd ? (ps == 0 ? 0 : (ps == 1 ? 1 : 3)) : 2 * ps;
        const int cnt = (odd && ps != 1) ? 1 : 2;
        const int ha = g * 4 + hfirst;
        for (int ks = 0; ks < 8; ks++) {
          {
            mbar_wait(empty0 + ring.slot * 8, ring.phase ^ 1);
            uint32_t fb = full0 + ring.slot * 8;
            uint32_t dst = sbase + ring.slot * SLOT_BYTES;
            mbar_expect_tx(fb, SLOT_BYTES);
            tma_load_2d(dst, &mx, ks * 128, b * 128, fb);
            tma_load_2d(dst + 16384, &mx, ks * 128 + 64, b * 128, fb);
            ring.advance();
          }
          if (cnt == 2) {
            for (int half = 0; half < 2; half++) {
              mbar_wait(empty0 + ring.slot * 8, ring.phase ^ 1);
              uint32_t fb = full0 + ring.slot * 8;
              uint32_t dst = sbase + ring.slot * SLOT_BYTES;
              mbar_expect_tx(fb, SLOT_BYTES);
#pragma unroll
              for (int j = 0; j < 4; j++)
                tma_load_2d(dst + j * 8192, &mwq, ha * 128 + j * 64, ks * 128 + half * 64, fb);
              ring.advance();
            }
          } else {
            mbar_wait(empty0 + ring.slot * 8, ring.phase ^ 1);
            uint32_t fb = full0 + ring.slot * 8;
            uint32_t dst = sbase + ring.slot * SLOT_BYTES;
            mbar_expect_tx(fb, SLOT_BYTES);
#pragma unroll
            for (int j = 0; j < 4; j++)
              tma_load_2d(dst + (j >> 1) * 16384 + (j & 1) * 8192, &mwq, ha * 128 + (j >> 1) * 64,
                          ks * 128 + (j & 1) * 64, fb);
            ring.advance();
          }
        }
        for (int hh = 0; hh < cnt; hh++) {
          const int rowbase = (b * kH + ha + hh) * kSK;
          for (int it = 0; it < 8; it++) {
            const int isv = (it == 7) ? 1 : ((it >= 2) && (it & 1) == 0);
            const int c = isv ? ((it == 7) ? 3 : (it >> 1) - 1) : ((it + 1) >> 1);
            const CUtensorMap* mp = isv ? &mv : &mk;
            mbar_wait(empty0 + ring.slot * 8, ring.phase ^ 1);
            uint32_t fb = full0 + ring.slot * 8;
            uint32_t dst = sbase + ring.slot * SLOT_BYTES;
            mbar_expect_tx(fb, SLOT_BYTES);
            tma_load_2d_hint(dst, mp, 0, rowbase + c * 128, fb, pol_kv);
            tma_load_2d_hint(dst + 16384, mp, 64, rowbase + c * 128, fb, pol_kv);
            ring.advance();
          }
        }
      }
    }
  } else {
    asm volatile("setmaxnreg.inc.sync.aligned.u32 240;");
    const int cw = wg - 1;
    const int ctid = tid - 128;
    const int warp_in_wg = (tid >> 5) & 3;
    const uint32_t wscr_a = sbase + RING_BYTES + (uint32_t)(ctid >> 5) * 4096u;
    uint32_t* wscr = reinterpret_cast<uint32_t*>(smem_raw + (wscr_a - smem_u32(smem_raw)));
    const float kScaleLog2 = 0.08838834764831845f * 1.4426950408889634f;
    Ring ring;
    TS(0);
    for (int ps = 0; ps < npass; ps++) {
      const int hfirst = odd ? (ps == 0 ? 0 : (ps == 1 ? 1 : 3)) : 2 * ps;
      const int cnt = (odd && ps != 1) ? 1 : 2;
      const int ha = g * 4 + hfirst;
      uint32_t q[32];
      if (cnt == 2) {
        float acc[128];
#pragma unroll
        for (int i = 0; i < 128; i++) acc[i] = 0.f;
        gemm_consume_128x256(acc, 8, ring, sbase, full0, empty0, cw, lane);
#pragma unroll
        for (int i = 0; i < 32; i++) {
          q[i] = pack_bf16(acc[2 * i], acc[2 * i + 1]);
          wscr[i * 32 + lane] = pack_bf16(acc[64 + 2 * i], acc[64 + 2 * i + 1]);
        }
      } else {
        float acc[64];
#pragma unroll
        for (int i = 0; i < 64; i++) acc[i] = 0.f;
        gemm_consume_128x128(acc, 8, ring, sbase, full0, empty0, cw, lane);
#pragma unroll
        for (int i = 0; i < 32; i++) q[i] = pack_bf16(acc[2 * i], acc[2 * i + 1]);
      }
      TS(1 + ps * 3);
      for (int hh = 0; hh < cnt; hh++) {
        const int h = ha + hh;
        float o[64];
#pragma unroll
        for (int i = 0; i < 64; i++) o[i] = 0.f;
        float m0 = -INFINITY, m1 = -INFINITY, l0 = 0.f, l1 = 0.f;
        float s[64];
        uint32_t pfrag[32];
        float a0, a1;
        auto softmax_exp = [&]() {
          float mx0 = s[0], mx1 = s[2];
#pragma unroll
          for (int j = 0; j < 16; j++) {
            mx0 = fmaxf(mx0, fmaxf(s[4 * j], s[4 * j + 1]));
            mx1 = fmaxf(mx1, fmaxf(s[4 * j + 2], s[4 * j + 3]));
          }
          mx0 = fmaxf(mx0, __shfl_xor_sync(0xffffffffu, mx0, 1));
          mx0 = fmaxf(mx0, __shfl_xor_sync(0xffffffffu, mx0, 2));
          mx1 = fmaxf(mx1, __shfl_xor_sync(0xffffffffu, mx1, 1));
          mx1 = fmaxf(mx1, __shfl_xor_sync(0xffffffffu, mx1, 2));
          const float mn0 = fmaxf(m0, mx0), mn1 = fmaxf(m1, mx1);
          a0 = ex2((m0 - mn0) * kScaleLog2);
          a1 = ex2((m1 - mn1) * kScaleLog2);
          const float mc0 = mn0 * kScaleLog2, mc1 = mn1 * kScaleLog2;
          m0 = mn0;
          m1 = mn1;
          float rs0 = 0.f, rs1 = 0.f;
#pragma unroll
          for (int j = 0; j < 16; j++) {
            s[4 * j] = ex2(fmaf(s[4 * j], kScaleLog2, -mc0));
            s[4 * j + 1] = ex2(fmaf(s[4 * j + 1], kScaleLog2, -mc0));
            s[4 * j + 2] = ex2(fmaf(s[4 * j + 2], kScaleLog2, -mc1));
            s[4 * j + 3] = ex2(fmaf(s[4 * j + 3], kScaleLog2, -mc1));
            rs0 += s[4 * j] + s[4 * j + 1];
            rs1 += s[4 * j + 2] + s[4 * j + 3];
          }
          l0 = l0 * a0 + rs0;
          l1 = l1 * a1 + rs1;
        };
        auto issue_s = [&]() {
          uint32_t kslot = ring.slot;
          mbar_wait(full0 + kslot * 8, ring.phase);
          ring.advance();
          uint32_t kaddr = sbase + kslot * SLOT_BYTES;
          fence_regs_u(q);
          wgmma_fence();
#pragma unroll
          for (int kk = 0; kk < 8; kk++) {
            wgmma_m64n128k16_rs_tb0(s, q[4 * kk], q[4 * kk + 1], q[4 * kk + 2], q[4 * kk + 3],
                                    desc_kmajor(kaddr + (kk >> 2) * 16384 + (kk & 3) * 32), kk > 0 ? 1 : 0);
          }
          wgmma_commit();
          return kslot;
        };
        {
          uint32_t kslot = issue_s();
          wgmma_wait<0>();
          fence_regs(s);
          fence_regs_u(q);
          if (lane == 0) mbar_arrive(empty0 + kslot * 8);
          softmax_exp();
#pragma unroll
          for (int i = 0; i < 32; i++) pfrag[i] = pack_bf16(s[2 * i], s[2 * i + 1]);
        }
#pragma unroll
        for (int c = 0; c < 4; c++) {
          uint32_t kslot = 0;
          if (c < 3) kslot = issue_s();
          uint32_t vslot = ring.slot;
          mbar_wait(full0 + vslot * 8, ring.phase);
          ring.advance();
          uint32_t vaddr = sbase + vslot * SLOT_BYTES;
          fence_regs(o);
          fence_regs_u(pfrag);
          wgmma_fence();
#pragma unroll
          for (int kk = 0; kk < 8; kk++) {
            wgmma_m64n128k16_rs_tb1(o, pfrag[4 * kk], pfrag[4 * kk + 1], pfrag[4 * kk + 2], pfrag[4 * kk + 3],
                                    desc_mnmajor(vaddr + kk * 2048, 16384), 1);
          }
          wgmma_commit();
          if (c < 3) {
            wgmma_wait<1>();
            fence_regs(s);
            fence_regs_u(q);
            if (lane == 0) mbar_arrive(empty0 + kslot * 8);
            softmax_exp();
          }
          wgmma_wait<0>();
          fence_regs(o);
          fence_regs_u(pfrag);
          if (lane == 0) mbar_arrive(empty0 + vslot * 8);
          if (c < 3) {
#pragma unroll
            for (int j = 0; j < 16; j++) {
              o[4 * j] *= a0;
              o[4 * j + 1] *= a0;
              o[4 * j + 2] *= a1;
              o[4 * j + 3] *= a1;
            }
#pragma unroll
            for (int i = 0; i < 32; i++) pfrag[i] = pack_bf16(s[2 * i], s[2 * i + 1]);
          }
        }
        l0 += __shfl_xor_sync(0xffffffffu, l0, 1);
        l0 += __shfl_xor_sync(0xffffffffu, l0, 2);
        l1 += __shfl_xor_sync(0xffffffffu, l1, 1);
        l1 += __shfl_xor_sync(0xffffffffu, l1, 2);
        const float inv0 = 1.f / l0, inv1 = 1.f / l1;
        if (hh == 0 && cnt == 2) {
#pragma unroll
          for (int i = 0; i < 32; i++) q[i] = wscr[i * 32 + lane];
        }
        if (lane == 0) bulk_wait_read0();
        __syncwarp();
        {
          const int r0 = lane >> 2, qd = lane & 3;
#pragma unroll
          for (int j = 0; j < 16; j++) {
            const int sub = j >> 3, c8 = j & 7;
            wscr[sub * 512 + r0 * 32 + ((c8 ^ r0) << 2) + qd] = pack_bf16(o[4 * j] * inv0, o[4 * j + 1] * inv0);
            wscr[sub * 512 + (r0 + 8) * 32 + ((c8 ^ r0) << 2) + qd] =
                pack_bf16(o[4 * j + 2] * inv1, o[4 * j + 3] * inv1);
          }
          fence_proxy_async();
          __syncwarp();
          if (lane == 0) {
            const int row0 = b * 128 + cw * 64 + warp_in_wg * 16;
            tma_store_2d(&mos, h * 128, row0, wscr_a);
            tma_store_2d(&mos, h * 128 + 64, row0, wscr_a + 2048);
            bulk_commit();
          }
        }
        TS(2 + ps * 3 + hh);
      }
      if (lane == 0) bulk_wait_read0();
      __syncwarp();
    }
    if (lane == 0) bulk_wait0();
  }
}

__global__ void __cluster_dims__(2, 1, 1) __launch_bounds__(384, 1)
outproj_kernel(const __grid_constant__ CUtensorMap mo, const __grid_constant__ CUtensorMap mwo,
               __nv_bfloat16* __restrict__ out) {
  extern __shared__ uint8_t smem_raw[];
  __shared__ __align__(8) uint64_t full_bar[NSLOT];
  __shared__ __align__(8) uint64_t empty_bar[NSLOT];
  const uint32_t sbase = (smem_u32(smem_raw) + 1023u) & ~1023u;
  const uint32_t full0 = smem_u32(&full_bar[0]);
  const uint32_t empty0 = smem_u32(&empty_bar[0]);
  const int tid = threadIdx.x;
  const int wg = __shfl_sync(0xffffffffu, tid >> 7, 0);
  const int lane = tid & 31;
  const int rank = blockIdx.x & 1;
  const int tile = blockIdx.x >> 1;
  const int mt = tile & 15, nt = tile >> 4;
  const int k0 = rank * 2048;

  if (tid == 0) {
    for (int s = 0; s < NSLOT; s++) {
      mbar_init(full0 + s * 8, 1);
      mbar_init(empty0 + s * 8, 8);
    }
    asm volatile("fence.mbarrier_init.release.cluster;" ::: "memory");
    asm volatile("fence.proxy.async.shared::cta;" ::: "memory");
  }
  __syncthreads();

  if (wg == 0) {
    asm volatile("setmaxnreg.dec.sync.aligned.u32 24;");
    if (tid == 0) {
      Ring ring;
      asm volatile("griddepcontrol.wait;" ::: "memory");
      for (int ks = 0; ks < 16; ks++) {
        {
          mbar_wait(empty0 + ring.slot * 8, ring.phase ^ 1);
          uint32_t fb = full0 + ring.slot * 8;
          uint32_t dst = sbase + ring.slot * SLOT_BYTES;
          mbar_expect_tx(fb, SLOT_BYTES);
          tma_load_2d(dst, &mo, k0 + ks * 128, mt * 128, fb);
          tma_load_2d(dst + 16384, &mo, k0 + ks * 128 + 64, mt * 128, fb);
          ring.advance();
        }
        for (int half = 0; half < 2; half++) {
          mbar_wait(empty0 + ring.slot * 8, ring.phase ^ 1);
          uint32_t fb = full0 + ring.slot * 8;
          uint32_t dst = sbase + ring.slot * SLOT_BYTES;
          mbar_expect_tx(fb, SLOT_BYTES);
#pragma unroll
          for (int j = 0; j < 4; j++)
            tma_load_2d(dst + j * 8192, &mwo, nt * 256 + j * 64, k0 + ks * 128 + half * 64, fb);
          ring.advance();
        }
      }
    }
    __syncwarp();
    cluster_sync_all();
    cluster_sync_all();
  } else {
    asm volatile("setmaxnreg.inc.sync.aligned.u32 240;");
    const int cw = wg - 1;
    const int ctid = tid - 128;
    const int warp_in_wg = (tid >> 5) & 3;
    Ring ring;
    float acc[128];
#pragma unroll
    for (int i = 0; i < 128; i++) acc[i] = 0.f;
    TS(40);
    gemm_consume_128x256(acc, 16, ring, sbase, full0, empty0, cw, lane);
    TS(41);
    cluster_sync_all();
    TS(42);
    uint32_t raddr;
    asm volatile("mapa.shared::cluster.u32 %0, %1, %2;" : "=r"(raddr) : "r"(sbase), "r"(rank ^ 1));
    if (rank == 0) {
#pragma unroll
      for (int j = 0; j < 16; j++)
        asm volatile("st.shared::cluster.v4.f32 [%0], {%1, %2, %3, %4};" ::"r"(raddr + (uint32_t)(j * 4096 + ctid * 16)),
                     "f"(acc[64 + 4 * j]), "f"(acc[64 + 4 * j + 1]), "f"(acc[64 + 4 * j + 2]), "f"(acc[64 + 4 * j + 3])
                     : "memory");
    } else {
#pragma unroll
      for (int j = 0; j < 16; j++)
        asm volatile("st.shared::cluster.v4.f32 [%0], {%1, %2, %3, %4};" ::"r"(raddr + (uint32_t)(j * 4096 + ctid * 16)),
                     "f"(acc[4 * j]), "f"(acc[4 * j + 1]), "f"(acc[4 * j + 2]), "f"(acc[4 * j + 3])
                     : "memory");
    }
    cluster_sync_all();
    TS(43);
    {
      const float4* stage = reinterpret_cast<const float4*>(smem_raw + (sbase - smem_u32(smem_raw)));
      const int row = mt * 128 + cw * 64 + warp_in_wg * 16 + (lane >> 2);
      __nv_bfloat16* orow0 = out + (size_t)row * kD + nt * 256 + rank * 128 + (lane & 3) * 2;
      __nv_bfloat16* orow1 = orow0 + (size_t)8 * kD;
      if (rank == 0) {
#pragma unroll
        for (int j = 0; j < 16; j++) {
          float4 v = stage[j * 256 + ctid];
          float v0 = acc[4 * j] + v.x;
          float v1 = acc[4 * j + 1] + v.y;
          float v2 = acc[4 * j + 2] + v.z;
          float v3 = acc[4 * j + 3] + v.w;
          *reinterpret_cast<uint32_t*>(orow0 + 8 * j) = pack_bf16(v0, v1);
          *reinterpret_cast<uint32_t*>(orow1 + 8 * j) = pack_bf16(v2, v3);
        }
      } else {
#pragma unroll
        for (int j = 0; j < 16; j++) {
          float4 v = stage[j * 256 + ctid];
          float v0 = acc[64 + 4 * j] + v.x;
          float v1 = acc[64 + 4 * j + 1] + v.y;
          float v2 = acc[64 + 4 * j + 2] + v.z;
          float v3 = acc[64 + 4 * j + 3] + v.w;
          *reinterpret_cast<uint32_t*>(orow0 + 8 * j) = pack_bf16(v0, v1);
          *reinterpret_cast<uint32_t*>(orow1 + 8 * j) = pack_bf16(v2, v3);
        }
      }
    }
  }
}

typedef CUresult (*PFN_tmapEncodeTiled)(CUtensorMap*, CUtensorMapDataType, cuuint32_t, void*, const cuuint64_t*,
                                        const cuuint64_t*, const cuuint32_t*, const cuuint32_t*,
                                        CUtensorMapInterleave, CUtensorMapSwizzle, CUtensorMapL2promotion,
                                        CUtensorMapFloatOOBfill);

PFN_tmapEncodeTiled get_encode_fn() {
  static PFN_tmapEncodeTiled fn = nullptr;
  if (!fn) {
    void* p = nullptr;
    cudaDriverEntryPointQueryResult st;
    cudaGetDriverEntryPoint("cuTensorMapEncodeTiled", &p, cudaEnableDefault, &st);
    fn = (PFN_tmapEncodeTiled)p;
  }
  return fn;
}

CUtensorMap make_map(const void* base, uint64_t rows, uint64_t cols, uint32_t box_rows, uint32_t box_cols) {
  CUtensorMap m;
  cuuint64_t dims[2] = {cols, rows};
  cuuint64_t strides[1] = {cols * 2};
  cuuint32_t box[2] = {box_cols, box_rows};
  cuuint32_t estr[2] = {1, 1};
  get_encode_fn()(&m, CU_TENSOR_MAP_DATA_TYPE_BFLOAT16, 2, const_cast<void*>(base), dims, strides, box, estr,
                  CU_TENSOR_MAP_INTERLEAVE_NONE, CU_TENSOR_MAP_SWIZZLE_128B, CU_TENSOR_MAP_L2_PROMOTION_L2_128B,
                  CU_TENSOR_MAP_FLOAT_OOB_FILL_NONE);
  return m;
}

}

extern "C" void kernel_launch(void* const* d_in, const int* in_sizes, int n_in, void* d_out, int out_size) {
  (void)in_sizes;
  (void)n_in;
  (void)out_size;
  const void* x = d_in[0];
  const void* kc = d_in[1];
  const void* vc = d_in[2];
  const void* wq = d_in[3];
  const void* wo = d_in[4];
  void* optr = nullptr;
  cudaGetSymbolAddress(&optr, g_O);

  CUtensorMap mx = make_map(x, kM, kD, 128, 64);
  CUtensorMap mwq = make_map(wq, kD, kHD, 64, 64);
  CUtensorMap mk = make_map(kc, (uint64_t)kB * kH * kSK, kDH, 128, 64);
  CUtensorMap mv = make_map(vc, (uint64_t)kB * kH * kSK, kDH, 128, 64);
  CUtensorMap mo = make_map(optr, kM, kHD, 128, 64);
  CUtensorMap mos = make_map(optr, kM, kHD, 16, 64);
  CUtensorMap mwo = make_map(wo, kHD, kD, 64, 64);

  cudaFuncSetAttribute(attn_kernel, cudaFuncAttributeMaxDynamicSharedMemorySize, SMEM_A);
  cudaFuncSetAttribute(outproj_kernel, cudaFuncAttributeMaxDynamicSharedMemorySize, SMEM_B);

  attn_kernel<<<128, 384, SMEM_A>>>(mx, mwq, mk, mv, mos);
  {
    cudaLaunchConfig_t cfg = {};
    cfg.gridDim = dim3(128);
    cfg.blockDim = dim3(384);
    cfg.dynamicSmemBytes = SMEM_B;
    cfg.stream = 0;
    cudaLaunchAttribute attr[1];
    attr[0].id = cudaLaunchAttributeProgrammaticStreamSerialization;
    attr[0].val.programmaticStreamSerializationAllowed = 1;
    cfg.attrs = attr;
    cfg.numAttrs = 1;
    cudaLaunchKernelEx(&cfg, outproj_kernel, mo, mwo, reinterpret_cast<__nv_bfloat16*>(d_out));
  }
}
```
